```python
import torch

def _softmax(x, axis=-1):
    return torch.softmax(x, dim=axis)
def _gelu(x):
    return torch.nn.functional.gelu(x, approximate="tanh")
def _silu(x):
    return torch.nn.functional.silu(x)
def _sigmoid(x):
    return torch.sigmoid(x)
def _layernorm(x, axis=-1, eps=1e-5):
    m = x.mean(dim=axis, keepdim=True)
    v = x.var(dim=axis, keepdim=True, unbiased=False)
    return (x - m) / torch.sqrt(v + eps)
def _scatter_add(tgt, idx, src, axis=0):
    return tgt.clone().index_add_(axis, idx, src)
def _segment_sum(src, seg, n):
    out = torch.zeros((n,) + src.shape[1:], dtype=src.dtype)
    return out.index_add_(0, seg, src)
def _pad(x, pw):
    flat = tuple(v for pair in reversed(pw) for v in pair)
    return torch.nn.functional.pad(x, flat)

kernel_name = 'gated_mix__sliding_block__mixer_token_mlp__prompt'

def setup_inputs():

    _w = (lambda a: (lambda t: t.to(torch.bfloat16) if t.is_floating_point() else t)(torch.as_tensor(a)))
    def _A_setup():
        B, S, D = 1, 2048, 512
        return {
            "x": _w((lambda *s: torch.randn(*s, dtype=torch.bfloat16) * 0.05)(B, S, D)),
            "wqkv": _w((lambda *s: torch.randn(*s, dtype=torch.bfloat16) * 0.8)(D, 3 * D)),
            "wo": _w((lambda *s: torch.randn(*s, dtype=torch.bfloat16) * 0.05)(D, D)),
        }
    _A_in = _A_setup()

    def _B_setup():
        B, S, D, F = 1, 2048, 512, 1792
        return {
            "x": _w((lambda *s: torch.randn(*s, dtype=torch.bfloat16) * 0.05)(B, S, D)),
            "w1": _w((lambda *s: torch.randn(*s, dtype=torch.bfloat16) * 3.2)(S, F) * (S ** -0.5)),
            "b1": _w((lambda *s: torch.randn(*s, dtype=torch.bfloat16) * 3.2)(F) * 0.02),
            "w2": _w((lambda *s: torch.randn(*s, dtype=torch.bfloat16) * 0.1)(F, S) * (F ** -0.5)),
            "b2": _w((lambda *s: torch.randn(*s, dtype=torch.bfloat16) * 0.1)(S) * 0.02),
        }
    _B_in = _B_setup()

    return {
        "A_x": _A_in["x"],
        "A_wqkv": _A_in["wqkv"],
        "A_wo": _A_in["wo"],
        "B_x": _B_in["x"],
        "B_w1": _B_in["w1"],
        "B_b1": _B_in["b1"],
        "B_w2": _B_in["w2"],
        "B_b2": _B_in["b2"],
        "gate_w": _w((lambda *s: torch.randn(*s, dtype=torch.bfloat16) * 0.05)(512) * 16.0),
    }

def reference(A_x, A_wqkv, A_wo, B_x, B_w1, B_b1, B_w2, B_b2, gate_w):
    def _A_ref(x, wqkv, wo):
        B, S, D = x.shape
        H = 32; Dh = D // H; W = 256
        qkv = (lambda x, *d: x.permute(*d))((x @ wqkv).reshape(B, S, 3, H, Dh), 2, 0, 3, 1, 4)
        q, k, v = qkv[0], qkv[1], qkv[2]
        scores = torch.einsum("bhqd,bhkd->bhqk", q, k) * (Dh ** -0.5)
        idx = torch.arange(S)
        mask = (idx[:, None] - idx[None, :] >= 0) & (idx[:, None] - idx[None, :] < W)
        scores = torch.where(mask[None, None], scores, -1e9)
        p = _softmax(scores, axis=-1)
        o = torch.einsum("bhqk,bhkd->bhqd", p, v)
        return (lambda x, *d: x.permute(*d))(o, 0, 2, 1, 3).reshape(B, S, D) @ wo

    def _B_ref(x, w1, b1, w2, b2):
        B, S, D = x.shape
        h = _layernorm(x, axis=-1)
        u = torch.einsum("bsd,sf->bdf", h, w1) + b1
        u = _gelu(u)
        y = torch.einsum("bdf,fs->bds", u, w2) + b2
        return (lambda x, *d: x.permute(*d))(y, 0, 2, 1)

    x = A_x
    g = _sigmoid((x * gate_w).sum(-1, keepdims=True))
    a = _A_ref(x, A_wqkv, A_wo)
    b = _B_ref(x, B_w1, B_b1, B_w2, B_b2)
    return g * a + (1 - g) * b
```

```cpp
#include <cuda_runtime.h>
#include <cuda_bf16.h>
#include <cuda.h>
#include <stdint.h>

namespace {

constexpr int S_ = 2048, D_ = 512, F_ = 1792;
constexpr int NTHREADS = 640;
constexpr int NFIRST = 2;
constexpr int QDELAY = 800;
constexpr int LNSLEEP = 2000;
constexpr bool LOCALFIRST = true;
constexpr int QDEFER = 1;
constexpr int NH = 2;

constexpr int C_DONE = 0, C_LN = 1  , C_U = 9  , C_O = 17  , C_KV = 81  , C_CHK = 209, C_NUM = 210;
constexpr size_t G_CNT = 0;
constexpr size_t G_EZ = 28672;
constexpr size_t G_H = 36864 + 28672;
constexpr size_t G_UT = G_H + 32 * 4 * 16384;
constexpr size_t G_OT = G_UT + 28 * 4 * 16384;
constexpr size_t G_KV = G_OT + 8 * 16 * 16384;
constexpr size_t G_END = G_KV + 16 * 16 * 16384;
__device__ __align__(1024) uint8_t g_scr[G_END];

struct alignas(64) Maps { CUtensorMap mX, mWqkv, mW1, mW2, mWo; };

constexpr int SM_B = 0;
constexpr int SM_A = 131072;
constexpr int SM_KV = SM_A;
constexpr int SM_X = SM_A + 81920;
constexpr int SM_BAR = SM_A + 98304;
constexpr int SM_MISC = SM_BAR + 352;
constexpr int SM_B1 = SM_BAR + 384;
constexpr int SM_EZ = SM_BAR + 512;
constexpr int SM_OG = SM_BAR + 1024;
constexpr int SM_ONES = SM_BAR + 1536;
constexpr int SM_B2 = SM_BAR + 2048;
constexpr int SMEM_BYTES = SM_BAR + 2560;
__host__ __device__ constexpr int qbuf(int k) { return k >= 5 ? qbuf(k - 4) : (k < 3 ? k * 40960 : SM_A + (k - 3) * 40960); }
constexpr int B_FULL = 0, Q_FULL = 4, B_EMPTY = 12, G1_END = 16, Q_EMPTY = 17, A_KVW = 25, A_KVF = 26, A_DONE = 30, AUX = 32, LN_ALL = 34, A_KVW2 = 35,
              A_KMAX = 36, AUX0 = 37, X_FULL = 38  , U_ST = 40, O_RDY = 41;
constexpr unsigned long long BAR_C8 = (0xFull << B_EMPTY) | (0xFFull << Q_EMPTY) | (1ull << A_KVW) | (1ull << A_KVW2) | (3ull << A_DONE) | (1ull << G1_END) | (1ull << U_ST);

__device__ __forceinline__ uint32_t smem_u32(const void* p) { return (uint32_t)__cvta_generic_to_shared(p); }
__device__ __forceinline__ void mbar_init(uint32_t bar, uint32_t cnt) { asm volatile("mbarrier.init.shared::cta.b64 [%0], %1;" ::"r"(bar), "r"(cnt)); }
__device__ __forceinline__ void mbar_expect_tx(uint32_t bar, uint32_t bytes) {
  asm volatile("mbarrier.arrive.expect_tx.shared::cta.b64 _, [%0], %1;" ::"r"(bar), "r"(bytes) : "memory");
}
__device__ __forceinline__ void mbar_arrive(uint32_t bar) { asm volatile("mbarrier.arrive.shared::cta.b64 _, [%0];" ::"r"(bar) : "memory"); }
__device__ __forceinline__ uint32_t mapa(uint32_t addr, uint32_t cta) {
  uint32_t r; asm volatile("mapa.shared::cluster.u32 %0, %1, %2;" : "=r"(r) : "r"(addr), "r"(cta)); return r;
}
__device__ __forceinline__ void mbar_wait(uint32_t bar, uint32_t parity) {
  asm volatile("{\n.reg .pred p;\n.reg .u32 n;\nmov.u32 n, 0;\n"
               "W_%=:\nmbarrier.try_wait.parity.shared::cta.b64 p, [%0], %1;\n@p bra D_%=;\n"
               "add.u32 n, n, 1;\nsetp.lt.u32 p, n, 262144;\n@p bra W_%=;\nD_%=:\n}" ::"r"(bar), "r"(parity) : "memory");
}
__device__ __forceinline__ void mbar_wait_cluster(uint32_t bar, uint32_t parity) {
  asm volatile("{\n.reg .pred p;\n.reg .u32 n;\nmov.u32 n, 0;\n"
               "W_%=:\nmbarrier.try_wait.parity.acquire.cluster.shared::cta.b64 p, [%0], %1;\n@p bra D_%=;\n"
               "add.u32 n, n, 1;\nsetp.lt.u32 p, n, 262144;\n@p bra W_%=;\nD_%=:\n}" ::"r"(bar), "r"(parity) : "memory");
}
__device__ __forceinline__ void tma2d(uint32_t dst, const CUtensorMap* m, int c0, int c1, uint32_t bar) {
  asm volatile("cp.async.bulk.tensor.2d.shared::cluster.global.mbarrier::complete_tx::bytes [%0], [%1, {%3, %4}], [%2];"
               ::"r"(dst), "l"(m), "r"(bar), "r"(c0), "r"(c1) : "memory");
}
__device__ __forceinline__ void tma3d(uint32_t dst, const CUtensorMap* m, int c0, int c1, int c2, uint32_t bar) {
  asm volatile("cp.async.bulk.tensor.3d.shared::cluster.global.mbarrier::complete_tx::bytes [%0], [%1, {%3, %4, %5}], [%2];"
               ::"r"(dst), "l"(m), "r"(bar), "r"(c0), "r"(c1), "r"(c2) : "memory");
}
__device__ __forceinline__ void tma4d(uint32_t dst, const CUtensorMap* m, int c0, int c1, int c2, int c3, uint32_t bar) {
  asm volatile("cp.async.bulk.tensor.4d.shared::cluster.global.mbarrier::complete_tx::bytes [%0], [%1, {%3, %4, %5, %6}], [%2];"
               ::"r"(dst), "l"(m), "r"(bar), "r"(c0), "r"(c1), "r"(c2), "r"(c3) : "memory");
}
__device__ __forceinline__ void bulk_load(uint32_t dst, const void* src, uint32_t bytes, uint32_t bar) {
  asm volatile("cp.async.bulk.shared::cluster.global.mbarrier::complete_tx::bytes [%0], [%1], %2, [%3];" ::"r"(dst), "l"(src), "r"(bytes), "r"(bar) : "memory");
}
__device__ __forceinline__ void bulk_store(void* dst, uint32_t src, uint32_t bytes) {
  asm volatile("cp.async.bulk.global.shared::cta.bulk_group [%0], [%1], %2;" ::"l"(dst), "r"(src), "r"(bytes) : "memory");
}
__device__ __forceinline__ void bulk_commit() { asm volatile("cp.async.bulk.commit_group;" ::: "memory"); }
__device__ __forceinline__ void bulk_wait() { asm volatile("cp.async.bulk.wait_group 0;" ::: "memory"); }
__device__ __forceinline__ void fence_async_smem() { asm volatile("fence.proxy.async.shared::cta;" ::: "memory"); }
__device__ __forceinline__ void fence_async_global() { asm volatile("fence.proxy.async.global;" ::: "memory"); }
__device__ __forceinline__ unsigned ld_acquire(const unsigned* p) {
  unsigned v; asm volatile("ld.acquire.gpu.global.u32 %0, [%1];" : "=r"(v) : "l"(p) : "memory"); return v;
}
__device__ __forceinline__ void publish_add(unsigned* p, unsigned v) {
  asm volatile("fence.proxy.async.global;\nred.release.gpu.global.add.u32 [%0], %1;" ::"l"(p), "r"(v) : "memory");
}
__device__ __forceinline__ unsigned poll_ge(const unsigned* p, unsigned target) {
  unsigned v, n = 0;
  while ((v = ld_acquire(p)) < target && ++n < (1u << 20)) {}
  fence_async_global();
  return v;
}
__device__ __forceinline__ bool mbar_test(uint32_t bar, uint32_t parity) {
  uint32_t ok;
  asm volatile("{\n.reg .pred p;\nmbarrier.test_wait.parity.shared::cta.b64 p, [%1], %2;\nselp.u32 %0, 1, 0, p;\n}" : "=r"(ok) : "r"(bar), "r"(parity) : "memory");
  return ok;
}
__device__ __forceinline__ void prefetch_map(const CUtensorMap* m) { asm volatile("prefetch.tensormap [%0];" ::"l"(m) : "memory"); }
__device__ __forceinline__ void named_bar(int id, int n) { asm volatile("bar.sync %0, %1;" ::"r"(id), "r"(n) : "memory"); }
__device__ __forceinline__ void wg_fence() { asm volatile("wgmma.fence.sync.aligned;" ::: "memory"); }
__device__ __forceinline__ void wg_commit() { asm volatile("wgmma.commit_group.sync.aligned;" ::: "memory"); }
template <int N> __device__ __forceinline__ void wg_wait() { asm volatile("wgmma.wait_group.sync.aligned %0;" ::"n"(N) : "memory"); }
template <int N> __device__ __forceinline__ void reg_fence(float (&d)[N]) {
#pragma unroll
  for (int i = 0; i < N; i++) asm volatile("" : "+f"(d[i])::"memory");
}
template <int N> __device__ __forceinline__ void reg_fence(uint32_t (&d)[N]) {
#pragma unroll
  for (int i = 0; i < N; i++) asm volatile("" : "+r"(d[i])::"memory");
}
__device__ __forceinline__ uint64_t mk_desc(uint32_t addr, uint32_t lbo, uint32_t sbo, uint32_t swz) {
  uint32_t lo = ((addr & 0x3FFFF) >> 4) | ((lbo >> 4) << 16);
  uint32_t hi = (sbo >> 4) | (swz << 30);
  return ((uint64_t)hi << 32) | lo;
}
__device__ __forceinline__ uint32_t pack_bf16(float lo, float hi) {
  uint32_t r; asm("cvt.rn.bf16x2.f32 %0, %1, %2;" : "=r"(r) : "f"(hi), "f"(lo)); return r;
}
__device__ __forceinline__ uint32_t sq2_bf16(uint32_t a, uint32_t b) {
  uint32_t r; asm("{\n.reg .b32 t;\nmul.rn.bf16x2 t, %1, %1;\nfma.rn.bf16x2 %0, %2, %2, t;\n}" : "=r"(r) : "r"(a), "r"(b)); return r;
}
__device__ __forceinline__ uint32_t max_bf16(uint32_t a, uint32_t b) {
  uint32_t r; asm("max.NaN.bf16x2 %0, %1, %2;" : "=r"(r) : "r"(a), "r"(b)); return r;
}
__device__ __forceinline__ float ex2(float x) { float r; asm("ex2.approx.ftz.f32 %0, %1;" : "=f"(r) : "f"(x)); return r; }
__device__ __forceinline__ float rcp(float x) { float r; asm("rcp.approx.ftz.f32 %0, %1;" : "=f"(r) : "f"(x)); return r; }
__device__ __forceinline__ float bf_lo(uint32_t v) { return __uint_as_float(v << 16); }
__device__ __forceinline__ float bf_hi(uint32_t v) { return __uint_as_float(v & 0xFFFF0000u); }
__device__ __forceinline__ void stsm4(uint32_t addr, uint32_t a, uint32_t b, uint32_t c, uint32_t d) {
  asm volatile("stmatrix.sync.aligned.m8n8.x4.shared.b16 [%0], {%1, %2, %3, %4};" ::"r"(addr), "r"(a), "r"(b), "r"(c), "r"(d) : "memory");
}
__device__ __forceinline__ void stsm4t(uint32_t addr, uint32_t a, uint32_t b, uint32_t c, uint32_t d) {
  asm volatile("stmatrix.sync.aligned.m8n8.x4.trans.shared.b16 [%0], {%1, %2, %3, %4};" ::"r"(addr), "r"(a), "r"(b), "r"(c), "r"(d) : "memory");
}
__device__ __forceinline__ uint32_t movm_t(uint32_t a) {
  uint32_t r; asm volatile("movmatrix.sync.aligned.m8n8.trans.b16 %0, %1;" : "=r"(r) : "r"(a)); return r;
}
__device__ __forceinline__ void st_async4(uint32_t raddr, uint32_t a, uint32_t b, uint32_t c, uint32_t d, uint32_t rbar) {
  asm volatile("st.async.weak.shared::cluster.mbarrier::complete_tx::bytes.v4.b32 [%0], {%1, %2, %3, %4}, [%5];"
               ::"r"(raddr), "r"(a), "r"(b), "r"(c), "r"(d), "r"(rbar) : "memory");
}
__device__ __forceinline__ uint4 ldg_nc(const uint4* p) {
  uint4 v; asm volatile("ld.global.nc.v4.u32 {%0, %1, %2, %3}, [%4];" : "=r"(v.x), "=r"(v.y), "=r"(v.z), "=r"(v.w) : "l"(p)); return v;
}
__device__ __forceinline__ uint4 lds128(uint32_t addr) {
  uint4 v; asm volatile("ld.shared.v4.u32 {%0, %1, %2, %3}, [%4];" : "=r"(v.x), "=r"(v.y), "=r"(v.z), "=r"(v.w) : "r"(addr) : "memory"); return v;
}
__device__ __forceinline__ void sts128(uint32_t addr, uint32_t a, uint32_t b, uint32_t c, uint32_t d) {
  asm volatile("st.shared.v4.u32 [%0], {%1, %2, %3, %4};" ::"r"(addr), "r"(a), "r"(b), "r"(c), "r"(d) : "memory");
}
__device__ __forceinline__ uint32_t lds32(uint32_t addr) { uint32_t v; asm volatile("ld.shared.u32 %0, [%1];" : "=r"(v) : "r"(addr) : "memory"); return v; }
__device__ __forceinline__ float lds32f(uint32_t addr) { return __uint_as_float(lds32(addr)); }
__device__ __forceinline__ uint32_t lds16(uint32_t addr) { uint16_t v; asm volatile("ld.shared.u16 %0, [%1];" : "=h"(v) : "r"(addr) : "memory"); return v; }
__device__ __forceinline__ void sts32(uint32_t addr, uint32_t v) { asm volatile("st.shared.u32 [%0], %1;" ::"r"(addr), "r"(v) : "memory"); }

template <int TA, int TB, int SCALE_D, long long OA, long long OB>
__device__ __forceinline__ void wgmma_ss_n128(float (&d)[64], uint64_t da, uint64_t db) {
  asm volatile(
      "{\n.reg .pred p;\n.reg .b64 xa, xb;\nsetp.ne.b32 p, %66, 0;\nadd.s64 xa, %64, %69;\nadd.s64 xb, %65, %70;\n"
      "wgmma.mma_async.sync.aligned.m64n128k16.f32.bf16.bf16 {"
      "%0, %1, %2, %3, %4, %5, %6, %7, %8, %9, %10, %11, %12, %13, %14, %15, %16, %17, %18, %19, %20, %21, "
      "%22, %23, %24, %25, %26, %27, %28, %29, %30, %31, %32, %33, %34, %35, %36, %37, %38, %39, %40, %41, "
      "%42, %43, %44, %45, %46, %47, %48, %49, %50, %51, %52, %53, %54, %55, %56, %57, %58, %59, %60, %61, "
      "%62, %63"
      "}, xa, xb, p, 1, 1, %67, %68;\n}\n"
      : "+f"(d[0]), "+f"(d[1]), "+f"(d[2]), "+f"(d[3]), "+f"(d[4]), "+f"(d[5]), "+f"(d[6]), "+f"(d[7]),
        "+f"(d[8]), "+f"(d[9]), "+f"(d[10]), "+f"(d[11]), "+f"(d[12]), "+f"(d[13]), "+f"(d[14]), "+f"(d[15]),
        "+f"(d[16]), "+f"(d[17]), "+f"(d[18]), "+f"(d[19]), "+f"(d[20]), "+f"(d[21]), "+f"(d[22]),
        "+f"(d[23]), "+f"(d[24]), "+f"(d[25]), "+f"(d[26]), "+f"(d[27]), "+f"(d[28]), "+f"(d[29]),
        "+f"(d[30]), "+f"(d[31]), "+f"(d[32]), "+f"(d[33]), "+f"(d[34]), "+f"(d[35]), "+f"(d[36]),
        "+f"(d[37]), "+f"(d[38]), "+f"(d[39]), "+f"(d[40]), "+f"(d[41]), "+f"(d[42]), "+f"(d[43]),
        "+f"(d[44]), "+f"(d[45]), "+f"(d[46]), "+f"(d[47]), "+f"(d[48]), "+f"(d[49]), "+f"(d[50]),
        "+f"(d[51]), "+f"(d[52]), "+f"(d[53]), "+f"(d[54]), "+f"(d[55]), "+f"(d[56]), "+f"(d[57]),
        "+f"(d[58]), "+f"(d[59]), "+f"(d[60]), "+f"(d[61]), "+f"(d[62]), "+f"(d[63])
      : "l"(da), "l"(db), "n"(SCALE_D), "n"(TA), "n"(TB), "n"(OA), "n"(OB));
}
template <int TA, int TB, int SCALE_D, long long OA, long long OB>
__device__ __forceinline__ void wgmma_ss_n64acc(float (&d)[32], uint64_t da, uint64_t db) {
  asm volatile(
      "{\n.reg .pred p;\n.reg .b64 xa, xb;\nsetp.ne.b32 p, %34, 0;\nadd.s64 xa, %32, %37;\nadd.s64 xb, %33, %38;\n"
      "wgmma.mma_async.sync.aligned.m64n64k16.f32.bf16.bf16 {"
      "%0, %1, %2, %3, %4, %5, %6, %7, %8, %9, %10, %11, %12, %13, %14, %15, %16, %17, %18, %19, %20, %21, "
      "%22, %23, %24, %25, %26, %27, %28, %29, %30, %31"
      "}, xa, xb, p, 1, 1, %35, %36;\n}\n"
      : "+f"(d[0]), "+f"(d[1]), "+f"(d[2]), "+f"(d[3]), "+f"(d[4]), "+f"(d[5]), "+f"(d[6]), "+f"(d[7]),
        "+f"(d[8]), "+f"(d[9]), "+f"(d[10]), "+f"(d[11]), "+f"(d[12]), "+f"(d[13]), "+f"(d[14]), "+f"(d[15]),
        "+f"(d[16]), "+f"(d[17]), "+f"(d[18]), "+f"(d[19]), "+f"(d[20]), "+f"(d[21]), "+f"(d[22]),
        "+f"(d[23]), "+f"(d[24]), "+f"(d[25]), "+f"(d[26]), "+f"(d[27]), "+f"(d[28]), "+f"(d[29]),
        "+f"(d[30]), "+f"(d[31])
      : "l"(da), "l"(db), "n"(SCALE_D), "n"(TA), "n"(TB), "n"(OA), "n"(OB));
}
template <int TB, long long OB>
__device__ __forceinline__ void wgmma_rs_n64(float (&d)[32], uint32_t a0, uint32_t a1, uint32_t a2, uint32_t a3, uint64_t db) {
  asm volatile(
      "{\n.reg .b64 xb;\nadd.s64 xb, %36, %38;\n"
      "wgmma.mma_async.sync.aligned.m64n64k16.f32.bf16.bf16 {"
      "%0, %1, %2, %3, %4, %5, %6, %7, %8, %9, %10, %11, %12, %13, %14, %15, %16, %17, %18, %19, %20, %21, "
      "%22, %23, %24, %25, %26, %27, %28, %29, %30, %31"
      "}, {%32, %33, %34, %35}, xb, 0, 1, 1, %37;\n}\n"
      : "=f"(d[0]), "=f"(d[1]), "=f"(d[2]), "=f"(d[3]), "=f"(d[4]), "=f"(d[5]), "=f"(d[6]), "=f"(d[7]),
        "=f"(d[8]), "=f"(d[9]), "=f"(d[10]), "=f"(d[11]), "=f"(d[12]), "=f"(d[13]), "=f"(d[14]), "=f"(d[15]),
        "=f"(d[16]), "=f"(d[17]), "=f"(d[18]), "=f"(d[19]), "=f"(d[20]), "=f"(d[21]), "=f"(d[22]),
        "=f"(d[23]), "=f"(d[24]), "=f"(d[25]), "=f"(d[26]), "=f"(d[27]), "=f"(d[28]), "=f"(d[29]),
        "=f"(d[30]), "=f"(d[31])
      : "r"(a0), "r"(a1), "r"(a2), "r"(a3), "l"(db), "n"(TB), "n"(OB));
}
template <int TB, long long OB>
__device__ __forceinline__ void wgmma_rs_n24(float (&d)[12], uint32_t a0, uint32_t a1, uint32_t a2, uint32_t a3, uint64_t db) {
  asm volatile(
      "{\n.reg .b64 xb;\nadd.s64 xb, %16, %18;\n"
      "wgmma.mma_async.sync.aligned.m64n24k16.f32.bf16.bf16 {"
      "%0, %1, %2, %3, %4, %5, %6, %7, %8, %9, %10, %11"
      "}, {%12, %13, %14, %15}, xb, 1, 1, 1, %17;\n}\n"
      : "+f"(d[0]), "+f"(d[1]), "+f"(d[2]), "+f"(d[3]), "+f"(d[4]), "+f"(d[5]), "+f"(d[6]), "+f"(d[7]),
        "+f"(d[8]), "+f"(d[9]), "+f"(d[10]), "+f"(d[11])
      : "r"(a0), "r"(a1), "r"(a2), "r"(a3), "l"(db), "n"(TB), "n"(OB));
}

template <int SLOT>
__device__ __forceinline__ void b_step(float (&acc)[64], uint32_t sb, uint64_t da, uint64_t db, uint32_t par, uint32_t par_next, bool& ready,
                                       bool elect) {
  constexpr int O = SLOT * 2048;
  const uint32_t bars = sb + SM_BAR;
  if (!ready) mbar_wait(bars + 8 * (B_FULL + SLOT), par);
  wg_fence();
  wgmma_ss_n128<1, 1, 1, O, O>(acc, da, db);
  wgmma_ss_n128<1, 1, 1, O + 128, O + 128>(acc, da, db);
  wg_commit();
  wg_wait<0>(); wg_fence();
  wgmma_ss_n128<1, 1, 1, O + 256, O + 256>(acc, da, db);
  wgmma_ss_n128<1, 1, 1, O + 384, O + 384>(acc, da, db);
  wg_commit();
  ready = __all_sync(~0u, mbar_test(bars + 8 * (B_FULL + ((SLOT + 1) & 3)), par_next));
  wg_wait<0>();
  if (elect) mbar_arrive(bars + 8 * (B_EMPTY + SLOT));
}
template <int HI, int SLOT> __device__ __forceinline__ void b_half(float (&acc)[32], uint64_t da, uint64_t db) {
  constexpr int O = SLOT * 2048;
  wgmma_ss_n64acc<1, 1, 1, O, O + HI * 512>(acc, da, db);
  wgmma_ss_n64acc<1, 1, 1, O + 128, O + 128 + HI * 512>(acc, da, db);
  wgmma_ss_n64acc<1, 1, 1, O + 256, O + 256 + HI * 512>(acc, da, db);
  wgmma_ss_n64acc<1, 1, 1, O + 384, O + 384 + HI * 512>(acc, da, db);
}
template <int PH>
__device__ __forceinline__ void b_gemm(float (&acc)[64], float (&lo)[32], uint32_t sb, int warp, int lane, uint32_t peer) {
  const uint32_t bars = sb + SM_BAR;
  const uint64_t da = mk_desc(sb + SM_B + (warp >> 2) * 8192, 8192, 1024, 1);
  const uint64_t db = mk_desc(sb + SM_B + 16384, 8192, 1024, 1);
  const bool elect = lane == 0;
  __syncwarp();
  reg_fence(acc);
  bool ready = false;
  constexpr int NK = PH == 1 ? 16 : 18, NF = NK - NH;
#pragma unroll 1
  for (uint32_t r = 0; r < NF / 4; r++) {
    const uint32_t par = r & 1;
    b_step<0>(acc, sb, da, db, par, par, ready, elect); b_step<1>(acc, sb, da, db, par, par, ready, elect);
    b_step<2>(acc, sb, da, db, par, par, ready, elect); b_step<3>(acc, sb, da, db, par, par ^ 1, ready, elect);
  }
  if (NF % 4 > 0) b_step<0>(acc, sb, da, db, 1, 1, ready, elect);
  if (NF % 4 > 1) b_step<1>(acc, sb, da, db, 1, 1, ready, elect);
  if (NF % 4 > 2) b_step<2>(acc, sb, da, db, 1, 1, ready, elect);
  const uint32_t mine = sb + SM_X + warp * 2048 + lane * 16;
  const uint32_t rdst = mapa(mine, peer), rbar = mapa(bars + 8 * (X_FULL + PH - 1), peer);
  reg_fence(acc);
  float hi[32];
#pragma unroll
  for (int i = 0; i < 32; i++) asm volatile("add.f32 %0, %1, 0f00000000;" : "=f"(hi[i]) : "f"(acc[32 + i]));
  if (!ready) mbar_wait(bars + 8 * (B_FULL + NF % 4), (NF / 4) & 1);
  if (NH == 3) {
    wg_fence();
    b_half<1, NF % 4>(hi, da, db);
    wg_commit();
    mbar_wait(bars + 8 * (B_FULL + (NK - 2) % 4), ((NK - 2) / 4) & 1);
  }
  mbar_wait(bars + 8 * (B_FULL + (NK - 1) % 4), ((NK - 1) / 4) & 1);
  wg_fence();
  b_half<1, (NK - 2) % 4>(hi, da, db);
  b_half<1, (NK - 1) % 4>(hi, da, db);
  wg_commit();
#pragma unroll
  for (int i = 0; i < 32; i++) asm volatile("add.f32 %0, %1, 0f00000000;" : "=f"(lo[i]) : "f"(acc[i]));
  float og0 = 1.f, og1 = 1.f;
  if (PH == 2) { og0 = lds32f(sb + SM_OG + (warp * 16 + (lane >> 2)) * 4); og1 = lds32f(sb + SM_OG + (warp * 16 + (lane >> 2)) * 4 + 32); }
  wg_wait<0>();
  reg_fence(hi);
  if (PH == 2) {
#pragma unroll
    for (int j = 0; j < 8; j++) { hi[4 * j] *= og0; hi[4 * j + 1] *= og0; hi[4 * j + 2] *= og1; hi[4 * j + 3] *= og1; }
  }
#pragma unroll
  for (int j = 0; j < 4; j++)
    st_async4(rdst + j * 512, pack_bf16(hi[8 * j], hi[1 + 8 * j]), pack_bf16(hi[2 + 8 * j], hi[3 + 8 * j]), pack_bf16(hi[4 + 8 * j], hi[5 + 8 * j]),
              pack_bf16(hi[6 + 8 * j], hi[7 + 8 * j]), rbar);
  reg_fence(lo);
  wg_fence();
  if (NH == 3) b_half<0, NF % 4>(lo, da, db);
  b_half<0, (NK - 2) % 4>(lo, da, db);
  b_half<0, (NK - 1) % 4>(lo, da, db);
  wg_commit();
  wg_wait<0>();
  reg_fence(lo);
  if (PH == 1 && lane <= NH) mbar_arrive(bars + 8 * (lane < NH ? B_EMPTY + 3 - lane : G1_END));
  mbar_wait_cluster(bars + 8 * (X_FULL + PH - 1), 0);
#pragma unroll
  for (int j = 0; j < 4; j++) {
    const uint4 v = lds128(mine + j * 512);
    float* a = &lo[8 * j];
    a[0] = fmaf(a[0], og0, bf_lo(v.x)); a[1] = fmaf(a[1], og0, bf_hi(v.x)); a[2] = fmaf(a[2], og1, bf_lo(v.y)); a[3] = fmaf(a[3], og1, bf_hi(v.y));
    a[4] = fmaf(a[4], og0, bf_lo(v.z)); a[5] = fmaf(a[5], og0, bf_hi(v.z)); a[6] = fmaf(a[6], og1, bf_lo(v.w)); a[7] = fmaf(a[7], og1, bf_hi(v.w));
  }
}

__device__ __forceinline__ float gelu_tanh(float x) {
  const float z = x * fmaf(0.0356774081363f, x * x, 0.7978845608029f);
  float t; asm("tanh.approx.f32 %0, %1;" : "=f"(t) : "f"(z));
  const float hx = 0.5f * x;
  return fmaf(hx, t, hx);
}

template <int H, int B> __device__ __forceinline__ void issue_qk(float (&s)[32], const uint32_t (&q)[8], uint64_t dk) {
  wgmma_rs_n64<0, B * 512 + H * 128>(s, q[4 * H], q[4 * H + 1], q[4 * H + 2], q[4 * H + 3], dk);
}
template <int H, int B> __device__ __forceinline__ void issue_pv(float (&o)[12], const uint32_t (&p)[16], uint64_t dv) {
  wgmma_rs_n24<1, -65535ll * (B * 512 + H * 128)>(o, p[0], p[1], p[2], p[3], dv);
  wgmma_rs_n24<1, -65535ll * (B * 512 + H * 128 + 32)>(o, p[4], p[5], p[6], p[7], dv);
  wgmma_rs_n24<1, -65535ll * (B * 512 + H * 128 + 64)>(o, p[8], p[9], p[10], p[11], dv);
  wgmma_rs_n24<1, -65535ll * (B * 512 + H * 128 + 96)>(o, p[12], p[13], p[14], p[15], dv);
}
__device__ __forceinline__ void exps(float (&s)[32]) {
#pragma unroll
  for (int i = 0; i < 32; i++) s[i] = ex2(s[i]);
}
__device__ __forceinline__ void pack_p(const float (&s)[32], uint32_t (&p)[16]) {
#pragma unroll
  for (int i = 0; i < 16; i++) p[i] = pack_bf16(s[2 * i], s[2 * i + 1]);
}
__device__ __forceinline__ void zero_if(uint32_t (&p)[16], bool dead) {
  if (dead) {
#pragma unroll
    for (int i = 0; i < 16; i++) asm volatile("mov.b32 %0, 0;" : "+r"(p[i]));
  }
  reg_fence(p);
}
struct AttnCtx { uint32_t dq[8]; uint64_t dk, dv; uint32_t kvf, mk; int w, wg, bmin; };
__device__ __forceinline__ void turn_wait(int wg) { asm volatile("bar.sync %0, 256;" ::"r"(6 + wg) : "memory"); }
__device__ __forceinline__ void turn_pass(int wg) { asm volatile("bar.arrive %0, 256;" ::"r"(7 - wg) : "memory"); }
template <int B> __device__ __forceinline__ void attn_wide(float (&o0)[12], float (&o1)[12], const AttnCtx& c) {
  float s0[32], s1[32];
  uint32_t p0[16], p1[16];
  const int region = (c.wg + B) >> 1;
  if (region < 2 && B >= c.bmin) mbar_wait(c.kvf + 8 * region, 0);
  wg_fence();
  issue_qk<0, B>(s0, c.dq, c.dk); issue_qk<1, B>(s1, c.dq, c.dk);
  wg_commit();
  turn_wait(c.wg);
  wg_wait<0>();
  reg_fence(s0); reg_fence(s1);
  exps(s0); exps(s1);
  reg_fence(s0); reg_fence(s1);
  turn_pass(c.wg);
  pack_p(s0, p0); pack_p(s1, p1);
  if (B == 0 || B == 4) {
#pragma unroll
    for (int sb = 0; sb < 4; sb++) {
      const uint32_t lt = sb < c.w ? ~0u : 0u, le = sb <= c.w ? ~0u : 0u, dg = sb == c.w ? c.mk : lt;
      const uint32_t m[4] = {dg, le, lt, dg};
#pragma unroll
      for (int i = 0; i < 4; i++) { p0[4 * sb + i] &= B ? m[i] : ~m[i]; p1[4 * sb + i] &= B ? m[i] : ~m[i]; }
    }
  }
  zero_if(p0, B < c.bmin); zero_if(p1, B < c.bmin);
  wg_fence();
  issue_pv<0, B>(o0, p0, c.dv); issue_pv<1, B>(o1, p1, c.dv);
  wg_commit(); wg_wait<0>();
}
template <int H> __device__ __forceinline__ void attn_edge(float (&o)[12], const AttnCtx& c) {
  float s0[32], s1[32];
  uint32_t p0[16], p1[16];
  if (H == 0 && c.bmin == 0) mbar_wait(c.kvf, 0);
  wg_fence();
  issue_qk<H, 4>(s0, c.dq, c.dk); issue_qk<H, 0>(s1, c.dq, c.dk);
  wg_commit();
  turn_wait(c.wg);
  wg_wait<0>();
  reg_fence(s0); reg_fence(s1);
  const int t0 = c.w + (c.mk & 1), t1 = c.w + (c.mk >> 31);
#pragma unroll
  for (int sb = 0; sb < 4; sb++) {
    const bool k[8] = {sb < t0, sb < t1, sb <= c.w, sb <= c.w, sb < c.w, sb < c.w, sb < t0, sb < t1};
#pragma unroll
    for (int i = 0; i < 8; i++) s0[8 * sb + i] = k[i] ? s0[8 * sb + i] : s1[8 * sb + i];
  }
  exps(s0);
  reg_fence(s0);
  turn_pass(c.wg);
#pragma unroll
  for (int sb = 0; sb < 4; sb++) {
    const uint32_t lt = sb < c.w ? ~0u : 0u, le = sb <= c.w ? ~0u : 0u, dg = sb == c.w ? c.mk : lt;
    const uint32_t m[4] = {dg, le, lt, dg};
#pragma unroll
    for (int i = 0; i < 4; i++) {
      const uint32_t pk = pack_bf16(s0[8 * sb + 2 * i], s0[8 * sb + 2 * i + 1]);
      p0[4 * sb + i] = pk & m[i]; p1[4 * sb + i] = pk & ~m[i];
    }
  }
  reg_fence(p0); zero_if(p1, c.bmin > 0);
  wg_fence();
  issue_pv<H, 4>(o, p0, c.dv); issue_pv<H, 0>(o, p1, c.dv);
  wg_commit(); wg_wait<0>();
}
__device__ __forceinline__ void attn_slow(const AttnCtx& c, int hh, int lane, float (&o)[12]) {
  const float NEG = __int_as_float(0xFF800000);
  const int t0 = c.w + (c.mk & 1), t1 = c.w + (c.mk >> 31);
  float m0 = NEG, m1 = NEG, s[32];
  uint32_t p[16], qq[8];
#pragma unroll
  for (int i = 0; i < 8; i++) qq[i] = hh ? c.dq[4 + (i & 3)] : c.dq[i & 3];
  reg_fence(qq);
#pragma unroll
  for (int i = 0; i < 12; i++) o[i] = 0.f;
#pragma unroll 1
  for (int b = 4; b >= c.bmin; b--) {
    const int off = b * 512 + hh * 128;
    wg_fence();
    issue_qk<0, 0>(s, qq, c.dk + off);
    wg_commit(); wg_wait<0>(); reg_fence(s);
    const bool edge = b == 0 || b == 4, inv = b == 0;
#pragma unroll
    for (int sb = 0; sb < 4; sb++) {
      const bool ka = !edge || ((sb < t0) != inv), kb = !edge || ((sb < t1) != inv), kc = !edge || ((sb <= c.w) != inv), kd = !edge || ((sb < c.w) != inv);
      s[8 * sb] = ka ? s[8 * sb] : NEG;         s[8 * sb + 1] = kb ? s[8 * sb + 1] : NEG;
      s[8 * sb + 2] = kc ? s[8 * sb + 2] : NEG; s[8 * sb + 3] = kc ? s[8 * sb + 3] : NEG;
      s[8 * sb + 4] = kd ? s[8 * sb + 4] : NEG; s[8 * sb + 5] = kd ? s[8 * sb + 5] : NEG;
      s[8 * sb + 6] = ka ? s[8 * sb + 6] : NEG; s[8 * sb + 7] = kb ? s[8 * sb + 7] : NEG;
    }
    float x0 = m0, x1 = m1;
#pragma unroll
    for (int j = 0; j < 8; j++) { x0 = fmaxf(x0, fmaxf(s[4 * j], s[4 * j + 1])); x1 = fmaxf(x1, fmaxf(s[4 * j + 2], s[4 * j + 3])); }
    x0 = fmaxf(x0, __shfl_xor_sync(~0u, x0, 1)); x0 = fmaxf(x0, __shfl_xor_sync(~0u, x0, 2));
    x1 = fmaxf(x1, __shfl_xor_sync(~0u, x1, 1)); x1 = fmaxf(x1, __shfl_xor_sync(~0u, x1, 2));
    const float a0 = ex2(m0 - x0), a1 = ex2(m1 - x1);
    m0 = x0; m1 = x1;
#pragma unroll
    for (int j = 0; j < 3; j++) { o[4 * j] *= a0; o[4 * j + 1] *= a0; o[4 * j + 2] *= a1; o[4 * j + 3] *= a1; }
#pragma unroll
    for (int j = 0; j < 8; j++) { s[4 * j] -= x0; s[4 * j + 1] -= x0; s[4 * j + 2] -= x1; s[4 * j + 3] -= x1; }
    exps(s);
    pack_p(s, p);
    reg_fence(p);
    reg_fence(o);
    wg_fence();
    issue_pv<0, 0>(o, p, c.dv - (uint64_t)off * 65535u);
    wg_commit(); wg_wait<0>(); reg_fence(o);
  }
}

__device__ __forceinline__ void finalize_o(const float (&o)[12], float ea, float eb, uint32_t& p0, uint32_t& p1, uint32_t& p2, uint32_t& p3) {
  const float ra = ea * rcp(o[8]), rb = eb * rcp(o[10]);
  p0 = pack_bf16(o[0] * ra, o[1] * ra); p1 = pack_bf16(o[2] * rb, o[3] * rb);
  p2 = pack_bf16(o[4] * ra, o[5] * ra); p3 = pack_bf16(o[6] * rb, o[7] * rb);
}

constexpr float SCORE_BOUND2 = 3600.f;

template <int K, int PART> __device__ __forceinline__ void qkv_mma(float (&acc)[64], float (&aq)[32], uint64_t da0, uint64_t db0) {
  constexpr int o = qbuf(K) / 16;
  if (PART & 1) wgmma_ss_n128<0, 1, 1, o, o + 512>(acc, da0, db0);
  if (PART & 2) wgmma_ss_n64acc<0, 1, 1, o, o>(aq, da0, db0);
  if (PART & 1) wgmma_ss_n128<0, 1, 1, o + 2, o + 640>(acc, da0, db0);
  if (PART & 2) wgmma_ss_n64acc<0, 1, 1, o + 2, o + 128>(aq, da0, db0);
  if (PART & 1) wgmma_ss_n128<0, 1, 1, o + 4, o + 768>(acc, da0, db0);
  if (PART & 2) wgmma_ss_n64acc<0, 1, 1, o + 4, o + 256>(aq, da0, db0);
  if (PART & 1) wgmma_ss_n128<0, 1, 1, o + 6, o + 896>(acc, da0, db0);
  if (PART & 2) wgmma_ss_n64acc<0, 1, 1, o + 6, o + 384>(aq, da0, db0);
}
template <int K> __device__ __forceinline__ void qkv_step(float (&acc)[64], float (&aq)[32], uint32_t sb, uint64_t da0, uint64_t db0, int lane, uint32_t qpar) {
  const uint32_t bars = sb + SM_BAR;
  mbar_wait(bars + 8 * (Q_FULL + K), K < NFIRST ? qpar : 0);
  wg_fence();
  qkv_mma<K, (K < 8 - QDEFER ? 3 : 1)>(acc, aq, da0, db0);
  wg_commit();
  wg_wait<0>();
  if (K < 8 - QDEFER && lane == 0) mbar_arrive(bars + 8 * (Q_EMPTY + K));
}

__device__ __forceinline__ void finish_launch(unsigned* cnt, unsigned grid) {
  if (atomicAdd(cnt + C_DONE * 32, 1) == 63 + (grid >> 1))
    for (int i = 0; i < C_NUM; i++) *reinterpret_cast<uint4*>(cnt + i * 32) = make_uint4(0u, 0u, 0u, 0u);
}

template <bool USE_SMID>
__global__ void __cluster_dims__(2, 1, 1) __launch_bounds__(NTHREADS, 1)
fused_kernel(const __nv_bfloat16* __restrict__ x, const __nv_bfloat16* __restrict__ gate_w, uint8_t* __restrict__ scr, __nv_bfloat16* __restrict__ out,
             const __nv_bfloat16* __restrict__ b1, const __nv_bfloat16* __restrict__ b2, const __grid_constant__ Maps P) {
  unsigned* const cnt = reinterpret_cast<unsigned*>(scr + G_CNT);
  extern __shared__ __align__(1024) uint8_t smem_raw[];
  const uint32_t sb = smem_u32(smem_raw);
  const uint32_t bars = sb + SM_BAR;
  const int tid = threadIdx.x, warp = __shfl_sync(~0u, tid >> 5, 0), lane = tid & 31;
  uint32_t rank; asm volatile("mov.u32 %0, %%cluster_ctarank;" : "=r"(rank));
  uint32_t smid; asm volatile("mov.u32 %0, %%smid;" : "=r"(smid));
  uint4 v[2][2], gw[2];
  if (tid < 256 && blockIdx.x < 128) {
    const uint4* xr = reinterpret_cast<const uint4*>(x + (size_t)(16 * blockIdx.x + 2 * (tid >> 5)) * D_) + lane;
    v[0][0] = ldg_nc(xr); v[0][1] = ldg_nc(xr + 32); v[1][0] = ldg_nc(xr + 64); v[1][1] = ldg_nc(xr + 96);
    gw[0] = ldg_nc(reinterpret_cast<const uint4*>(gate_w) + lane); gw[1] = ldg_nc(reinterpret_cast<const uint4*>(gate_w) + 32 + lane);
  }
  const int tpc = smid >> 1;
  const int guess = !USE_SMID ? (int)(((blockIdx.x >> 1) & 7) * 8 + (blockIdx.x >> 4))
                              : (tpc < 32 ? (tpc & 7) * 8 + (tpc >> 3)
                                          : (tpc < 60 ? (1 + (tpc - 32) % 7) * 8 + 4 + (tpc - 32) / 7 : (tpc < 62 || tpc > 65 ? -1 : tpc - 58)));
  auto load_qkv = [&](int k, int it) {
    const int i16 = 2 * (it & 7) + rank;
    const uint32_t fb = bars + 8 * (Q_FULL + k);
    mbar_expect_tx(fb, 40960);
    tma2d(sb + qbuf(k), &P.mX, k * 64, (4 * (it >> 4) + (i16 & 3)) * 128, fb);
    tma3d(sb + qbuf(k) + 16384, &P.mWqkv, (4 * ((it >> 3) & 1) + (i16 >> 2)) * 64, k * 64, 0, fb);
  };
  if (warp == 17) {
    if (lane == 0) {
#pragma unroll
      for (int j = 0; j < 4; j++) mbar_init(bars + 8 * (Q_FULL + j), 1);
      asm volatile("fence.mbarrier_init.release.cluster;" ::: "memory");
    }
    __syncwarp();
    asm volatile("barrier.cluster.arrive.relaxed.aligned;" ::: "memory");
    if (lane == 0 && guess >= 0) {
#pragma unroll
      for (int k = 0; k < NFIRST; k++) load_qkv(k, guess);
    }
  } else {
    if (warp >= 8 && warp < 19 && lane == 0) {
#pragma unroll
      for (int j = 0; j < 4; j++) {
        const int i = ((warp + 6) % 11) * 4 + j;
        mbar_init(bars + 8 * i, ((BAR_C8 >> i) & 1) ? 8 : (i >= B_FULL && i < B_FULL + 4 ? 2 : (i == AUX || i == AUX0 ? 32 : 1)));
      }
      asm volatile("fence.mbarrier_init.release.cluster;" ::: "memory");
    }
    if (warp == 19) {
      if (lane < 5) sts32(sb + SM_MISC + 4 * lane, lane == 4 ? smid : 0);
      asm volatile("fence.release.sync_restrict::shared::cta.cluster;" ::: "memory");
    }
    __syncwarp();
    asm volatile("barrier.cluster.arrive.relaxed.aligned;" ::: "memory");
    if (warp == 19 && lane == 0) prefetch_map(&P.mW1);
  }

  if (warp < 8 && blockIdx.x < 128) {
    const int L = blockIdx.x;
    float f[2][16], sum[2], dot[2], var[2];
#pragma unroll
    for (int i = 0; i < 2; i++) {
      sum[i] = 0.f; dot[i] = 0.f; var[i] = 0.f;
#pragma unroll
      for (int h = 0; h < 2; h++) {
        const uint32_t xv[4] = {v[i][h].x, v[i][h].y, v[i][h].z, v[i][h].w};
#pragma unroll
        for (int c = 0; c < 4; c++) {
          f[i][8 * h + 2 * c] = bf_lo(xv[c]); f[i][8 * h + 2 * c + 1] = bf_hi(xv[c]);
          sum[i] += f[i][8 * h + 2 * c] + f[i][8 * h + 2 * c + 1];
        }
      }
    }
#pragma unroll
    for (int o = 16; o > 0; o >>= 1) { sum[0] += __shfl_xor_sync(~0u, sum[0], o); sum[1] += __shfl_xor_sync(~0u, sum[1], o); }
#pragma unroll
    for (int i = 0; i < 2; i++) {
      const float mean = sum[i] * (1.f / D_);
#pragma unroll
      for (int c = 0; c < 16; c++) { const float d = f[i][c] - mean; var[i] = fmaf(d, d, var[i]); }
    }
#pragma unroll
    for (int o = 16; o > 0; o >>= 1) { var[0] += __shfl_xor_sync(~0u, var[0], o); var[1] += __shfl_xor_sync(~0u, var[1], o); }
#pragma unroll
    for (int i = 0; i < 2; i++) {
      const float rs = rsqrtf(var[i] * (1.f / D_) + 1e-5f), sh = -sum[i] * (1.f / D_) * rs;
      const int row = 2 * warp + i;
#pragma unroll
      for (int h = 0; h < 2; h++) {
        const float* a = &f[i][8 * h];
        *reinterpret_cast<uint4*>(scr + G_H + (size_t)(L >> 2) * 65536 + (4 * h + (lane >> 3)) * 8192 + ((L & 3) * 16 + row) * 128 + (((lane ^ row) & 7) << 4)) =
            make_uint4(pack_bf16(fmaf(a[0], rs, sh), fmaf(a[1], rs, sh)), pack_bf16(fmaf(a[2], rs, sh), fmaf(a[3], rs, sh)),
                       pack_bf16(fmaf(a[4], rs, sh), fmaf(a[5], rs, sh)), pack_bf16(fmaf(a[6], rs, sh), fmaf(a[7], rs, sh)));
      }
    }
#pragma unroll
    for (int h = 0; h < 2; h++) {
      const uint32_t gv[4] = {gw[h].x, gw[h].y, gw[h].z, gw[h].w};
#pragma unroll
      for (int c = 0; c < 4; c++) {
#pragma unroll
        for (int i = 0; i < 2; i++) dot[i] = fmaf(f[i][8 * h + 2 * c], bf_lo(gv[c]), fmaf(f[i][8 * h + 2 * c + 1], bf_hi(gv[c]), dot[i]));
      }
    }
#pragma unroll
    for (int o = 16; o > 0; o >>= 1) { dot[0] += __shfl_xor_sync(~0u, dot[0], o); dot[1] += __shfl_xor_sync(~0u, dot[1], o); }
    if (lane < 2) reinterpret_cast<float*>(scr + G_EZ)[16 * L + 2 * warp + lane] = ex2(fminf(fmaxf(1.4426950408889634f * (lane ? dot[1] : dot[0]), -60.f), 60.f));
    if (warp == 0) {
      named_bar(1, 256);
      if (lane < 8) asm volatile("fence.proxy.async.global;\nred.release.gpu.global.add.u32 [%0], 1;" ::"l"(cnt + (C_LN + lane) * 32) : "memory");
      __syncwarp();
    } else {
      asm volatile("bar.arrive 1, 256;" ::: "memory");
    }
  }
  asm volatile("barrier.cluster.wait.acquire.aligned;" ::: "memory");

  int item = guess;
  uint32_t qpar = 0;
  bool owner = false;
  if (USE_SMID) {
    uint32_t psm; asm volatile("ld.shared::cluster.u32 %0, [%1];" : "=r"(psm) : "r"(mapa(sb + SM_MISC + 16, rank ^ 1)) : "memory");
    if (__any_sync(~0u, (psm >> 1) != (uint32_t)tpc)) item = -1;
    unsigned* chk = cnt + C_CHK * 32;
    owner = item >= 0;
    if (!owner) {
      if (tid == 608 && rank == 0) {
        asm volatile("red.release.gpu.global.add.u32 [%0], %1;" ::"l"(chk), "r"(0x10000u) : "memory");
        const unsigned v = poll_ge(chk, (gridDim.x >> 1) << 16);
        int pick = -1;
        if ((v & 0xFFFFu) < 64u) {
          unsigned long long free_ = ~((unsigned long long)ld_acquire(chk + 2) | ((unsigned long long)ld_acquire(chk + 3) << 32));
          for (unsigned t = atomicAdd(chk + 1, 1); t > 0 && free_; t--) free_ &= free_ - 1;
          pick = free_ ? __ffsll((long long)free_) - 1 : -1;
        }
        sts32(sb + SM_MISC + 20, pick);
        asm volatile("st.shared::cluster.u32 [%0], %1;" ::"r"(mapa(sb + SM_MISC + 20, 1)), "r"(pick) : "memory");
        if (pick < 0) finish_launch(cnt, gridDim.x);
      }
      __syncwarp();
      asm volatile("barrier.cluster.arrive.release.aligned;\nbarrier.cluster.wait.acquire.aligned;" ::: "memory");
      item = lds32(sb + SM_MISC + 20);
      if (guess >= 0) {
#pragma unroll
        for (int k = 0; k < NFIRST; k++) mbar_wait(bars + 8 * (Q_FULL + k), 0);
        qpar = 1;
        __syncthreads();
      }
      if (item < 0) return;
      if (warp == 17 && lane == 0) {
#pragma unroll
        for (int k = 0; k < NFIRST; k++) load_qkv(k, item);
      }
    }
    item = __shfl_sync(~0u, item, 0);
  }
  const int G = item >> 3, p = item & 7;
  const int idx16 = 2 * p + rank;
  const int rb = 4 * (G >> 1) + (idx16 & 3), hg = 4 * (G & 1) + (idx16 >> 2);
  const int dt = p & 3, ft = 2 * (G - 1) + (p >> 2), st = 2 * G + (p >> 2);

  if (warp < 8) {
    const int wg = warp >> 2, g = lane >> 2, q = lane & 3, mi = lane >> 3, r8 = lane & 7;
    float acc[64], res[32];
    mbar_wait(bars + 8 * AUX0, 0);
    if (G > 0) {
#pragma unroll
      for (int j = 0; j < 8; j++) {
        const uint32_t bias = lds32(sb + SM_B1 + 16 * j + 4 * q);
        acc[4 * j] = bf_lo(bias); acc[4 * j + 1] = bf_hi(bias); acc[4 * j + 2] = bf_lo(bias); acc[4 * j + 3] = bf_hi(bias);
      }
#pragma unroll
      for (int i = 32; i < 64; i++) acc[i] = 0.f;
      mbar_wait(bars + 8 * A_KVW, 0);
      b_gemm<1>(acc, res, sb, warp, lane, rank ^ 1);
      mbar_wait(bars + 8 * B_EMPTY, 1);
      const uint32_t stg = sb + SM_B + 16384;
      const uint32_t uo = (lane >> 1) * 128 + ((((warp & 3) * 2 + (lane & 1)) ^ ((lane >> 1) & 7)) << 4), us = stg + (wg ^ rank) * 8192 + uo;
      uint8_t* ug = scr + G_UT + (size_t)((ft * 2 + rank) * 4 + dt) * 16384 + wg * 8192 + uo;
      const uint32_t wbase = stg + (wg ^ rank) * 8192 + (8 * (mi >> 1) + r8) * 128 + ((((warp & 3) * 2 + (mi & 1)) ^ r8) << 4);
#pragma unroll
      for (int j = 0; j < 8; j += 2) {
        const uint32_t p0 = pack_bf16(gelu_tanh(res[4 * j]), gelu_tanh(res[4 * j + 1])), p1 = pack_bf16(gelu_tanh(res[4 * j + 2]), gelu_tanh(res[4 * j + 3]));
        const uint32_t p2 = pack_bf16(gelu_tanh(res[4 * j + 4]), gelu_tanh(res[4 * j + 5])), p3 = pack_bf16(gelu_tanh(res[4 * j + 6]), gelu_tanh(res[4 * j + 7]));
        stsm4t(wbase + j * 1024, p0, p1, p2, p3);
        __syncwarp();
        *reinterpret_cast<uint4*>(ug + j * 1024) = lds128(us + j * 1024);
      }
      fence_async_smem();
      __syncwarp();
      if (lane == 0) mbar_arrive(bars + 8 * U_ST);
    }
    const int row = warp * 16 + g;
    {
      const float r0 = bf_lo(lds16(sb + SM_B2 + row * 2)), r1 = bf_lo(lds16(sb + SM_B2 + row * 2 + 16));
#pragma unroll
      for (int j = 0; j < 8; j++) { acc[4 * j] = r0; acc[4 * j + 1] = r0; acc[4 * j + 2] = r1; acc[4 * j + 3] = r1; }
#pragma unroll
      for (int i = 32; i < 64; i++) acc[i] = 0.f;
    }
    mbar_wait(bars + 8 * AUX, 0);
    b_gemm<2>(acc, res, sb, warp, lane, rank ^ 1);
    {
      const uint32_t wstg = sb + SM_X + warp * 2048, wbase = wstg + (r8 + 8 * (mi & 1)) * 128;
      __nv_bfloat16* gptr = out + (size_t)(st * 128 + warp * 16 + mi) * D_ + dt * 128 + rank * 64 + r8 * 8;
      __syncwarp();
#pragma unroll
      for (int j = 0; j < 4; j++) {
        const float* a = &res[8 * j];
        stsm4(wbase + (((2 * j + (mi >> 1)) ^ r8) << 4), pack_bf16(a[0], a[1]), pack_bf16(a[2], a[3]), pack_bf16(a[4], a[5]), pack_bf16(a[6], a[7]));
      }
      __syncwarp();
#pragma unroll
      for (int i = 0; i < 4; i++)
        *reinterpret_cast<uint4*>(gptr + (size_t)i * 4 * D_) = lds128(wstg + (4 * i + mi) * 128 + ((r8 ^ ((4 * i + mi) & 7)) << 4));
    }
  } else if (warp < 16) {
    asm volatile("setmaxnreg.inc.sync.aligned.u32 128;");
    const int wg = (warp >> 2) & 1, w = warp & 3, mi = lane >> 3, r8 = lane & 7;
    if (warp == 8) sts128(sb + SM_ONES + 16 * lane, 0x3F803F80u, 0x3F803F80u, 0x3F803F80u, 0x3F803F80u);
    uint32_t qf[16];
    uint32_t qm = 0, km = 0;
    {
      float acc[64], av[32];
#pragma unroll
      for (int i = 0; i < 64; i++) acc[i] = 0.f;
#pragma unroll
      for (int i = 0; i < 32; i++) av[i] = 0.f;
      reg_fence(acc); reg_fence(av);
      const uint64_t da0 = mk_desc(sb + wg * 8192, 16, 1024, 1), db0 = mk_desc(sb + 16384, 8192, 1024, 1);
      qkv_step<0>(acc, av, sb, da0, db0, lane, qpar); qkv_step<1>(acc, av, sb, da0, db0, lane, qpar); qkv_step<2>(acc, av, sb, da0, db0, lane, qpar);
      qkv_step<3>(acc, av, sb, da0, db0, lane, qpar); qkv_step<4>(acc, av, sb, da0, db0, lane, qpar); qkv_step<5>(acc, av, sb, da0, db0, lane, qpar);
      qkv_step<6>(acc, av, sb, da0, db0, lane, qpar); qkv_step<7>(acc, av, sb, da0, db0, lane, qpar);
      reg_fence(acc); reg_fence(av);
      named_bar(2, 256);
      const uint32_t roff = (w * 16 + r8 + 8 * (mi & 1)) * 32 + (((mi >> 1) ^ ((r8 >> 2) & 1)) << 4);
      const float qs = 0.25f * 1.4426950408889634f;
      auto put_kv = [&](int h) {
        const uint32_t kvo = sb + SM_KV + (h >> 1) * 32768 + (4 + wg) * 8192 + (h & 1) * 2048 + roff;
        const float *k = &acc[8 * h], *v = &acc[32 + 8 * h];
        const uint32_t k0 = pack_bf16(k[0], k[1]), k1 = pack_bf16(k[2], k[3]), k2 = pack_bf16(k[4], k[5]), k3 = pack_bf16(k[6], k[7]);
        stsm4(kvo, k0, k1, k2, k3);
        stsm4(kvo + 4096, pack_bf16(v[0], v[1]), pack_bf16(v[2], v[3]), pack_bf16(v[4], v[5]), pack_bf16(v[6], v[7]));
        km = max_bf16(km, max_bf16(sq2_bf16(k0, k2), sq2_bf16(k1, k3)));
      };
      put_kv(0); put_kv(1);
      __syncwarp();
      if (rb < 15) {
        uint8_t* kg = scr + G_KV + (size_t)(hg * 16 + rb) * 32768 + wg * 8192 + w * 512 + lane * 16;
#pragma unroll
        for (int pl = 0; pl < 4; pl++)
          *reinterpret_cast<uint4*>(kg + pl * 2048) = lds128(sb + SM_KV + (4 + wg) * 8192 + pl * 2048 + w * 512 + lane * 16);
      }
      __syncwarp();
      if (lane == 0) mbar_arrive(bars + 8 * A_KVW);
      if (QDEFER) {
        wg_fence();
        if (QDEFER > 1) qkv_mma<6, 2>(acc, av, da0, db0);
        qkv_mma<7, 2>(acc, av, da0, db0);
        wg_commit();
      }
      put_kv(2); put_kv(3);
      if (QDEFER) {
        wg_wait<0>();
        reg_fence(av);
        if (lane < QDEFER) mbar_arrive(bars + 8 * (Q_EMPTY + 7 - lane));
      }
#pragma unroll
      for (int h = 0; h < 4; h++) {
        const float* a = &av[8 * h];
        const uint32_t q0 = pack_bf16(a[0] * qs, a[1] * qs), q1 = pack_bf16(a[2] * qs, a[3] * qs), q2 = pack_bf16(a[4] * qs, a[5] * qs),
                       q3 = pack_bf16(a[6] * qs, a[7] * qs);
        qf[4 * h] = q0; qf[4 * h + 1] = q1; qf[4 * h + 2] = q2; qf[4 * h + 3] = q3;
        qm = max_bf16(qm, max_bf16(sq2_bf16(q0, q2), sq2_bf16(q1, q3)));
      }
      fence_async_smem();
      named_bar(2, 256);
    }
    AttnCtx c;
    c.w = w; c.wg = wg; c.bmin = max(0, 4 - 2 * rb - wg);
    c.mk = (2 * (lane & 3) <= (lane >> 2) ? 0xFFFFu : 0u) | (2 * (lane & 3) + 1 <= (lane >> 2) ? 0xFFFF0000u : 0u);
    mbar_wait(bars + 8 * AUX, 0);
    const int row = wg * 64 + w * 16 + (lane >> 2);
    const float ea = lds32f(sb + SM_EZ + row * 4), eb = lds32f(sb + SM_EZ + row * 4 + 32);
    bool safe = true;
    if (wg == 0) turn_pass(0);
#pragma unroll 1
    for (int half = 0; half < 2; half++) {
      const uint32_t kvw = SM_KV + half * 32768 + wg * 8192;
      c.kvf = bars + 8 * (A_KVF + 2 * half);
#pragma unroll
      for (int i = 0; i < 8; i++) { c.dq[i] = qf[i]; qf[i] = qf[8 + i]; }
      reg_fence(c.dq);
      c.dk = mk_desc(sb + kvw, 16, 256, 3);
      c.dv = mk_desc(sb + kvw + 4096, SM_ONES - kvw - 4096, 256, 3);
      float o0[12], o1[12];
#pragma unroll
      for (int i = 0; i < 12; i++) { o0[i] = 0.f; o1[i] = 0.f; }
      reg_fence(o0); reg_fence(o1);

      if (half == 0) {
        if (LOCALFIRST) attn_wide<4>(o0, o1, c);
        float qn = bf_lo(qm) + bf_hi(qm), kn = bf_lo(km) + bf_hi(km);
        qn += __shfl_xor_sync(~0u, qn, 1); kn += __shfl_xor_sync(~0u, kn, 1);
        qn += __shfl_xor_sync(~0u, qn, 2); kn += __shfl_xor_sync(~0u, kn, 2);
        qm = __reduce_max_sync(~0u, __float_as_uint(qn)); km = __reduce_max_sync(~0u, __float_as_uint(kn));
        if (lane < 2) asm volatile("red.shared.max.u32 [%0], %1;" ::"r"(sb + SM_MISC + 4 * lane), "r"(lane ? km : qm) : "memory");
        __syncwarp();
        if (lane == 0) mbar_arrive(bars + 8 * A_KVW2);
      }
      attn_wide<3>(o0, o1, c); attn_wide<2>(o0, o1, c); attn_wide<1>(o0, o1, c);
      if (LOCALFIRST && half == 0) {
        attn_wide<0>(o0, o1, c);
      } else {
        attn_edge<0>(o0, c); attn_edge<1>(o1, c);
      }

      reg_fence(o0); reg_fence(o1);
      uint32_t po[8];
      finalize_o(o0, ea, eb, po[0], po[1], po[2], po[3]);
      finalize_o(o1, ea, eb, po[4], po[5], po[6], po[7]);
      {
        if (half == 0) {
          mbar_wait(bars + 8 * A_KMAX, 0);
          const uint4 mx = lds128(sb + SM_MISC);
          safe = __all_sync(~0u, __uint_as_float(mx.x) * __uint_as_float(max(mx.y, max(mx.z, mx.w))) <= SCORE_BOUND2);
        }
        if (!safe) {
#pragma unroll 1
          for (int hh = 0; hh < 2; hh++) {
            float os[12];
            attn_slow(c, hh, lane, os);
#pragma unroll
            for (int i = 0; i < 4; i++) po[i] = po[4 + i];
            finalize_o(os, ea, eb, po[4], po[5], po[6], po[7]);
          }
        }
      }
      {
        uint8_t* od = scr + G_OT + (size_t)((half * 4 + (hg >> 1)) * 16 + rb) * 16384 + (hg & 1) * 4096 + wg * 8192 + (lane >> 2) * 128 + (lane & 3) * 4;
#pragma unroll
        for (int i = 0; i < 8; i++)
          *reinterpret_cast<uint32_t*>(od + (i >> 1) * 1024 + (((2 * w + (i & 1)) ^ (lane >> 2)) << 4)) = movm_t(po[i]);
      }
      __syncwarp();
      if (lane == 0) mbar_arrive(bars + 8 * (A_DONE + half));
    }
    if (wg == 1) turn_wait(1);
  } else {
    asm volatile("setmaxnreg.dec.sync.aligned.u32 32;");
    auto slot_addr = [&](int i) { return sb + SM_B + (i & 3) * 32768; };
    auto full = [&](int i) { return bars + 8 * (B_FULL + (i & 3)); };
    auto wait_empty = [&](int i) {
      if (i < 4) mbar_wait(bars + 8 * (Q_EMPTY + (i == 0 ? 0 : (i == 1 ? 5 : 6))), 0);
      else mbar_wait(bars + 8 * (B_EMPTY + (i & 3)), ((i >> 2) & 1) ^ 1);
    };
    const int b0 = G > 0 ? 16 : 0, oa = G > 0 ? 17 : 0, ob = b0 + 16;
    auto u_tile = [&](int j) {
      const int t = (ft | 1) + j;
      return G == 0 ? j : (j == 0 ? ft ^ 1 : (t >= 14 ? t - 14 : t));
    };
    if (warp == 16) {
      unsigned last = 0;
      if (lane == 0) {
        __nanosleep(LNSLEEP);
        poll_ge(cnt + (C_LN + G) * 32, 128);
        if (G > 0) {
#pragma unroll 1
          for (int it = 0; it < 16; it++) {
            wait_empty(it); mbar_expect_tx(full(it), 16384);
            bulk_load(slot_addr(it), scr + G_H + (size_t)((rank * 16 + it) * 4 + dt) * 16384, 16384, full(it));
            if (it == 0) mbar_arrive(bars + 8 * LN_ALL);
          }
          mbar_wait(bars + 8 * U_ST, 0);
        } else {
          mbar_arrive(bars + 8 * LN_ALL);
        }
      }
      __syncwarp();
      if (G > 0 && lane < 9) publish_add(cnt + (lane < 8 ? (C_U + lane) * 32 : (C_KV + G * 16 + idx16) * 32 + 3), 1);
      if (G > 0 && lane == 0) mbar_arrive(full(16));
      if (lane == 0) {
#pragma unroll 1
        for (int it = oa + 2; it < ob; it++) {
          const int j = it - oa - 2, jj = u_tile(j);
          if (j == 0 && G > 0) continue;
          if (j == (G > 0)) { poll_ge(cnt + (C_U + G) * 32, 112); }
          const uint8_t* src = scr + G_UT + (size_t)((2 * jj + rank) * 4 + dt) * 16384;
          wait_empty(it); mbar_expect_tx(full(it), 16384);
          bulk_load(slot_addr(it) + 16384, src + rank * 8192, 8192, full(it));
          bulk_load(slot_addr(it) + 24576, src + 8192 - rank * 8192, 8192, full(it));
        }
        mbar_wait(bars + 8 * O_RDY, 0);
#pragma unroll 1
        for (int i = 0; i < 2; i++) {
          wait_empty(ob + i); mbar_expect_tx(full(ob + i), 16384);
          bulk_load(slot_addr(ob + i), scr + G_OT + (size_t)((4 + rank * 2 + i) * 16 + st) * 16384, 16384, full(ob + i));
        }
        last = atomicAdd(cnt + C_DONE * 32, 1) == 63 + (gridDim.x >> 1);
      }
      if (__shfl_sync(~0u, last, 0)) {
        for (int i = lane; i < C_NUM; i += 32) *reinterpret_cast<uint4*>(cnt + i * 32) = make_uint4(0u, 0u, 0u, 0u);
      }
    } else if (warp == 19) {
      if (lane == 0) {
        const int r0 = rank * 64, r1 = 64 - r0;
        mbar_expect_tx(bars + 8 * X_FULL, 16384); mbar_expect_tx(bars + 8 * (X_FULL + 1), 16384);
        if (owner && rank == 0) {
          atomicOr(cnt + C_CHK * 32 + 2 + (item >> 5), 1u << (item & 31));
          asm volatile("red.release.gpu.global.add.u32 [%0], %1;" ::"l"(cnt + C_CHK * 32), "r"(0x10001u) : "memory");
        }
        if (G > 0) {
#pragma unroll 1
          for (int it = 0; it < 16; it++) {
            wait_empty(it); mbar_expect_tx(full(it), 16384);
            tma2d(slot_addr(it) + 16384, &P.mW1, ft * 128 + r0, rank * 1024 + it * 64, full(it));
            tma2d(slot_addr(it) + 24576, &P.mW1, ft * 128 + r1, rank * 1024 + it * 64, full(it));
            if (it == 3) { prefetch_map(&P.mW2); prefetch_map(&P.mWo); }
          }
        }
#pragma unroll 1
        for (int it = b0; it < b0 + 18; it++) {
          wait_empty(it);
          mbar_expect_tx(full(it), 16384);
          if (it >= ob || (it >= oa && it < oa + 2)) {
            const int pass = it >= ob, i = it - (pass ? ob : oa);
            tma4d(slot_addr(it) + 16384, &P.mWo, dt * 128 + r0, 0, pass, rank * 4 + i * 2, full(it));
            tma4d(slot_addr(it) + 24576, &P.mWo, dt * 128 + r1, 0, pass, rank * 4 + i * 2, full(it));
          } else {
            const int jj = it < oa ? ft : u_tile(it - oa - 2);
            tma2d(slot_addr(it), &P.mW2, st * 128, (2 * jj + rank) * 64, full(it));
            tma2d(slot_addr(it) + 8192, &P.mW2, st * 128 + 64, (2 * jj + rank) * 64, full(it));
          }
        }
      }
    } else if (warp == 17) {
      if (lane == 0) {
        __nanosleep(QDELAY);
#pragma unroll
        for (int k = NFIRST; k < 8; k++) {
          if (k >= 5) mbar_wait(bars + 8 * (Q_EMPTY + k - 4), 0);
          load_qkv(k, item);
        }
        uint8_t* kvg = scr + G_KV + (size_t)(hg * 16 + rb) * 32768;
        mbar_wait(bars + 8 * A_KVW, 0);
        unsigned* kvflag = cnt + (C_KV + hg * 16 + rb) * 32;
        auto load_kv = [&](int pass, int n) {
          if (pass == 0) poll_ge(kvflag - n * 32, 1);
          const uint32_t fb = bars + 8 * (A_KVF + 2 * pass + 2 - n);
          mbar_expect_tx(fb, 16384);
          bulk_load(sb + SM_KV + pass * 32768 + (2 - n) * 16384, kvg - n * 32768 + pass * 16384, 16384, fb);
        };
        if (rb < 15) publish_add(kvflag, 1);
        mbar_wait(bars + 8 * (Q_EMPTY + 7), 0);
        if (rb >= 2) load_kv(0, 2);
        mbar_wait(bars + 8 * A_KVW2, 0);
        if (rb < 15) {
#pragma unroll 1
          for (int i = 0; i < 16384; i += 4096) {
            bulk_store(kvg + 16384 + i, sb + SM_KV + 65536 + i, 4096);
            bulk_commit(); bulk_wait();
          }
          publish_add(kvflag + 1, lds32(sb + SM_MISC + 4) + 1);
        }
        if (rb >= 1) { sts32(sb + SM_MISC + 8, poll_ge(kvflag - 32 + 1, 1)); load_kv(1, 1); }
        if (rb >= 2) sts32(sb + SM_MISC + 12, poll_ge(kvflag - 64 + 1, 1));
        mbar_arrive(bars + 8 * A_KMAX);
#pragma unroll 1
        for (int pass = 0; pass < 2; pass++) {
          mbar_wait(bars + 8 * (A_DONE + pass), 0);
          if (pass == 0 && rb >= 2) load_kv(1, 2);
          publish_add(cnt + (C_O + (pass * 16 + rb) * 2 + (hg >> 2)) * 32, 1);
        }
      }
    } else {
      if (G > 0) sts32(sb + SM_B1 + 4 * lane, __ldg(reinterpret_cast<const uint32_t*>(b1 + ft * 128 + rank * 64) + lane));
      const uint2 bb = __ldg(reinterpret_cast<const uint2*>(b2 + st * 128) + lane);
      sts32(sb + SM_B2 + 8 * lane, bb.x); sts32(sb + SM_B2 + 8 * lane + 4, bb.y);
      mbar_arrive(bars + 8 * AUX0);
      mbar_wait(bars + 8 * LN_ALL, 0);
      fence_async_global();
      const float4 ea = __ldcg(reinterpret_cast<const float4*>(scr + G_EZ + rb * 512) + lane);
      const float4 eo = __ldcg(reinterpret_cast<const float4*>(scr + G_EZ + st * 512) + lane);
      sts128(sb + SM_EZ + 16 * lane, __float_as_uint(ea.x), __float_as_uint(ea.y), __float_as_uint(ea.z), __float_as_uint(ea.w));
      sts128(sb + SM_OG + 16 * lane, __float_as_uint(rcp(1.f + eo.x)), __float_as_uint(rcp(1.f + eo.y)), __float_as_uint(rcp(1.f + eo.z)),
             __float_as_uint(rcp(1.f + eo.w)));
      mbar_arrive(bars + 8 * AUX);
      if (lane == 0) {
        if (rb >= 1) {
          mbar_wait(bars + 8 * (Q_EMPTY + 7), 0);
          poll_ge(cnt + (C_KV + hg * 16 + rb - 1) * 32, 1);
          mbar_expect_tx(bars + 8 * (A_KVF + 1), 16384);
          bulk_load(sb + SM_KV + 16384, scr + G_KV + (size_t)(hg * 16 + rb - 1) * 32768, 16384, bars + 8 * (A_KVF + 1));
        }
        if (G > 0) mbar_wait(bars + 8 * G1_END, 0);
        poll_ge(cnt + (C_O + st * 2 + rank) * 32, 4);
#pragma unroll 1
        for (int i = 0; i < 2; i++) {
          wait_empty(oa + i); mbar_expect_tx(full(oa + i), 16384);
          bulk_load(slot_addr(oa + i), scr + G_OT + (size_t)((rank * 2 + i) * 16 + st) * 16384, 16384, full(oa + i));
        }
        if (G > 0) {
          poll_ge(cnt + (C_KV + G * 16 + (idx16 ^ 8)) * 32 + 3, 1);
          const uint8_t* src = scr + G_UT + (size_t)((2 * (ft ^ 1) + rank) * 4 + dt) * 16384;
          wait_empty(19); mbar_expect_tx(full(19), 16384);
          bulk_load(slot_addr(19) + 16384, src + rank * 8192, 8192, full(19));
          bulk_load(slot_addr(19) + 24576, src + 8192 - rank * 8192, 8192, full(19));
        }
        poll_ge(cnt + (C_O + (16 + st) * 2 + rank) * 32, 4);
        mbar_arrive(bars + 8 * O_RDY);
      }
    }
  }
}

typedef CUresult (*EncodeFn)(CUtensorMap*, CUtensorMapDataType, cuuint32_t, void*, const cuuint64_t*, const cuuint64_t*, const cuuint32_t*,
                             const cuuint32_t*, CUtensorMapInterleave, CUtensorMapSwizzle, CUtensorMapL2promotion, CUtensorMapFloatOOBfill);

void make2d(EncodeFn enc, CUtensorMap* m, const void* ptr, uint64_t cols, uint64_t rows, uint32_t box_rows) {
  cuuint64_t dims[2] = {cols, rows}, strides[1] = {cols * 2};
  cuuint32_t box[2] = {64, box_rows}, es[2] = {1, 1};
  enc(m, CU_TENSOR_MAP_DATA_TYPE_BFLOAT16, 2, const_cast<void*>(ptr), dims, strides, box, es, CU_TENSOR_MAP_INTERLEAVE_NONE,
      CU_TENSOR_MAP_SWIZZLE_128B, CU_TENSOR_MAP_L2_PROMOTION_L2_256B, CU_TENSOR_MAP_FLOAT_OOB_FILL_NONE);
}

}

extern "C" void kernel_launch(void* const* d_in, const int* in_sizes, int n_in, void* d_out, int out_size) {
  void* fn = nullptr;
  cudaDriverEntryPointQueryResult qr;
  cudaGetDriverEntryPoint("cuTensorMapEncodeTiled", &fn, cudaEnableDefault, &qr);
  EncodeFn enc = (EncodeFn)fn;
  Maps P;
  make2d(enc, &P.mX, d_in[0], D_, S_, 128); make2d(enc, &P.mW1, d_in[4], F_, S_, 64);
  make2d(enc, &P.mW2, d_in[6], S_, F_, 64);
  {
    cuuint64_t dims[4] = {512, 32, 2, 8}, strides[3] = {1024, 32768, 65536};
    cuuint32_t box[4] = {64, 32, 1, 2}, es[4] = {1, 1, 1, 1};
    enc(&P.mWo, CU_TENSOR_MAP_DATA_TYPE_BFLOAT16, 4, d_in[2], dims, strides, box, es, CU_TENSOR_MAP_INTERLEAVE_NONE,
        CU_TENSOR_MAP_SWIZZLE_128B, CU_TENSOR_MAP_L2_PROMOTION_L2_256B, CU_TENSOR_MAP_FLOAT_OOB_FILL_NONE);
  }
  {
    cuuint64_t dims[3] = {512, 512, 3}, strides[2] = {3072, 1024};
    cuuint32_t box[3] = {64, 64, 3}, es[3] = {1, 1, 1};
    enc(&P.mWqkv, CU_TENSOR_MAP_DATA_TYPE_BFLOAT16, 3, d_in[1], dims, strides, box, es, CU_TENSOR_MAP_INTERLEAVE_NONE,
        CU_TENSOR_MAP_SWIZZLE_128B, CU_TENSOR_MAP_L2_PROMOTION_L2_256B, CU_TENSOR_MAP_FLOAT_OOB_FILL_NONE);
  }
  uint8_t* scr = nullptr;
  cudaGetSymbolAddress((void**)&scr, g_scr);
  int dev = 0, sms = 0;
  cudaGetDevice(&dev);
  cudaDeviceGetAttribute(&sms, cudaDevAttrMultiProcessorCount, dev);
  auto kern = sms == 132 ? fused_kernel<true> : fused_kernel<false>;
  cudaFuncSetAttribute(kern, cudaFuncAttributeMaxDynamicSharedMemorySize, SMEM_BYTES);
  kern<<<sms == 132 ? 132 : 128, NTHREADS, SMEM_BYTES, cudaStreamPerThread>>>(
      (const __nv_bfloat16*)d_in[0], (const __nv_bfloat16*)d_in[8], scr, (__nv_bfloat16*)d_out, (const __nv_bfloat16*)d_in[5], (const __nv_bfloat16*)d_in[7], P);
}
```
